```python
import torch

def _softmax(x, axis=-1):
    return torch.softmax(x, dim=axis)
def _gelu(x):
    return torch.nn.functional.gelu(x, approximate="tanh")
def _silu(x):
    return torch.nn.functional.silu(x)
def _sigmoid(x):
    return torch.sigmoid(x)
def _layernorm(x, axis=-1, eps=1e-5):
    m = x.mean(dim=axis, keepdim=True)
    v = x.var(dim=axis, keepdim=True, unbiased=False)
    return (x - m) / torch.sqrt(v + eps)
def _scatter_add(tgt, idx, src, axis=0):
    return tgt.clone().index_add_(axis, idx, src)
def _segment_sum(src, seg, n):
    out = torch.zeros((n,) + src.shape[1:], dtype=src.dtype)
    return out.index_add_(0, seg, src)
def _pad(x, pw):
    flat = tuple(v for pair in reversed(pw) for v in pair)
    return torch.nn.functional.pad(x, flat)

kernel_name = 'standalone__gqa_softmax__near_ridge'

def setup_inputs():

    _w = (lambda a: (lambda t: t.to(torch.bfloat16) if t.is_floating_point() else t)(torch.as_tensor(a)))
    B, Hq, Hkv, Sq, Sk, D = 16, 32, 16, 496, 512, 128
    return {
        "q": _w((lambda *s: torch.randn(*s, dtype=torch.bfloat16) * 0.8)(B, Hq, Sq, D)),
        "k": _w((lambda *s: torch.randn(*s, dtype=torch.bfloat16) * 0.8)(B, Hkv, Sk, D)),
        "v": _w((lambda *s: torch.randn(*s, dtype=torch.bfloat16) * 0.05)(B, Hkv, Sk, D)),
    }

def reference(q, k, v):
    B, Hq, Sq, D = q.shape
    Hkv = k.shape[1]
    rep = Hq // Hkv
    k = (lambda x, n, axis: torch.repeat_interleave(x, n, dim=axis))(k, rep, axis=1)
    v = (lambda x, n, axis: torch.repeat_interleave(x, n, dim=axis))(v, rep, axis=1)
    scale = D ** -0.5
    scores = torch.einsum("bhqd,bhkd->bhqk", q, k) * scale
    p = _softmax(scores, axis=-1)
    return torch.einsum("bhqk,bhkd->bhqd", p, v)
```

```cpp
#include <cuda_runtime.h>
#include <cuda_bf16.h>
#include <cuda.h>
#include <stdint.h>

namespace {

constexpr int HD      = 128;
constexpr int SQ      = 496;
constexpr int SK      = 512;
constexpr int HQ      = 32;
constexpr int HKV     = 16;
constexpr int BATCH   = 16;
constexpr int GROUPS  = BATCH * HKV;
constexpr int GROWS   = SQ * (HQ / HKV);
constexpr int UNITS_PER_GROUP = 4;
constexpr int NUNITS  = GROUPS * UNITS_PER_GROUP;
constexpr int NBLK    = SK / 128;

constexpr uint32_t TILE_BYTES = 128 * 128 * 2;
constexpr uint32_t SM_Q = 0;
constexpr uint32_t SM_K = 2 * TILE_BYTES;
constexpr uint32_t SM_V = 4 * TILE_BYTES;
constexpr uint32_t SM_O = 6 * TILE_BYTES;
constexpr uint32_t SM_BAR = 7 * TILE_BYTES;
constexpr uint32_t SMEM_BYTES = SM_BAR + 256 + 1024;

enum { B_QF = 0, B_QE = 2, B_KF = 4, B_KE = 6, B_VF = 8, B_VE = 10, B_NUM = 12 };

__device__ __forceinline__ uint32_t smem_u32(const void* p) {
    return (uint32_t)__cvta_generic_to_shared(p);
}
__device__ __forceinline__ void mbar_init(uint32_t bar, uint32_t cnt) {
    asm volatile("mbarrier.init.shared::cta.b64 [%0], %1;" ::"r"(bar), "r"(cnt) : "memory");
}
__device__ __forceinline__ void mbar_expect_tx(uint32_t bar, uint32_t bytes) {
    asm volatile("mbarrier.arrive.expect_tx.shared::cta.b64 _, [%0], %1;" ::"r"(bar), "r"(bytes) : "memory");
}
__device__ __forceinline__ void mbar_arrive(uint32_t bar) {
    asm volatile("mbarrier.arrive.shared::cta.b64 _, [%0];" ::"r"(bar) : "memory");
}
__device__ __forceinline__ void mbar_arrive_remote(uint32_t bar, uint32_t cta) {
    asm volatile(
        "{\n.reg .b32 ra;\n"
        "mapa.shared::cluster.u32 ra, %0, %1;\n"
        "mbarrier.arrive.release.cluster.shared::cluster.b64 _, [ra];\n}\n" ::"r"(bar), "r"(cta) : "memory");
}
__device__ __forceinline__ bool mbar_try(uint32_t bar, uint32_t parity) {
    uint32_t ok;
    asm volatile(
        "{\n.reg .pred p;\n"
        "mbarrier.try_wait.parity.shared::cta.b64 p, [%1], %2;\n"
        "selp.u32 %0, 1, 0, p;\n}\n" : "=r"(ok) : "r"(bar), "r"(parity) : "memory");
    return ok != 0;
}
__device__ __forceinline__ bool mbar_try_cluster(uint32_t bar, uint32_t parity) {
    uint32_t ok;
    asm volatile(
        "{\n.reg .pred p;\n"
        "mbarrier.try_wait.parity.acquire.cluster.shared::cta.b64 p, [%1], %2;\n"
        "selp.u32 %0, 1, 0, p;\n}\n" : "=r"(ok) : "r"(bar), "r"(parity) : "memory");
    return ok != 0;
}
__device__ __forceinline__ void mbar_wait(uint32_t bar, uint32_t parity) {
    if (mbar_try(bar, parity)) return;
    uint32_t n = 0;
    while (!mbar_try(bar, parity)) { if (++n > (1u << 22)) __trap(); }
}
__device__ __forceinline__ void mbar_wait_cluster(uint32_t bar, uint32_t parity) {
    if (mbar_try_cluster(bar, parity)) return;
    uint32_t n = 0;
    while (!mbar_try_cluster(bar, parity)) { if (++n > (1u << 22)) __trap(); }
}
__device__ __forceinline__ void tma_load_3d(uint32_t dst, const CUtensorMap* map, uint32_t bar, int c0, int c1, int c2) {
    asm volatile(
        "cp.async.bulk.tensor.3d.shared::cluster.global.mbarrier::complete_tx::bytes [%0], [%1, {%3, %4, %5}], [%2];"
        ::"r"(dst), "l"(map), "r"(bar), "r"(c0), "r"(c1), "r"(c2) : "memory");
}
__device__ __forceinline__ void tma_load_2d_mc(uint32_t dst, const CUtensorMap* map, uint32_t bar, int c0, int c1, uint16_t mask) {
    asm volatile(
        "cp.async.bulk.tensor.2d.shared::cluster.global.mbarrier::complete_tx::bytes.multicast::cluster [%0], [%1, {%3, %4}], [%2], %5;"
        ::"r"(dst), "l"(map), "r"(bar), "r"(c0), "r"(c1), "h"(mask) : "memory");
}
__device__ __forceinline__ void tma_store_3d(const CUtensorMap* map, uint32_t src, int c0, int c1, int c2) {
    asm volatile(
        "cp.async.bulk.tensor.3d.global.shared::cta.bulk_group [%0, {%2, %3, %4}], [%1];"
        ::"l"(map), "r"(src), "r"(c0), "r"(c1), "r"(c2) : "memory");
}
__device__ __forceinline__ void bar_sync(int id, int n) { asm volatile("bar.sync %0, %1;" ::"r"(id), "r"(n) : "memory"); }
__device__ __forceinline__ void bar_arrive(int id, int n) { asm volatile("bar.arrive %0, %1;" ::"r"(id), "r"(n) : "memory"); }

__device__ __forceinline__ void wgmma_fence() { asm volatile("wgmma.fence.sync.aligned;" ::: "memory"); }
__device__ __forceinline__ void wgmma_commit() { asm volatile("wgmma.commit_group.sync.aligned;" ::: "memory"); }
template <int N> __device__ __forceinline__ void wgmma_wait() { asm volatile("wgmma.wait_group.sync.aligned %0;" ::"n"(N) : "memory"); }

__device__ __forceinline__ uint64_t make_desc(uint32_t addr, uint32_t lbo, uint32_t sbo) {
    return (uint64_t)((addr & 0x3FFFF) >> 4) | ((uint64_t)(lbo >> 4) << 16) | ((uint64_t)(sbo >> 4) << 32) | (1ull << 62);
}

#define ACC64(a) \
    "+f"(a[0]), "+f"(a[1]), "+f"(a[2]), "+f"(a[3]), "+f"(a[4]), "+f"(a[5]), "+f"(a[6]), "+f"(a[7]), \
    "+f"(a[8]), "+f"(a[9]), "+f"(a[10]), "+f"(a[11]), "+f"(a[12]), "+f"(a[13]), "+f"(a[14]), "+f"(a[15]), \
    "+f"(a[16]), "+f"(a[17]), "+f"(a[18]), "+f"(a[19]), "+f"(a[20]), "+f"(a[21]), "+f"(a[22]), "+f"(a[23]), \
    "+f"(a[24]), "+f"(a[25]), "+f"(a[26]), "+f"(a[27]), "+f"(a[28]), "+f"(a[29]), "+f"(a[30]), "+f"(a[31]), \
    "+f"(a[32]), "+f"(a[33]), "+f"(a[34]), "+f"(a[35]), "+f"(a[36]), "+f"(a[37]), "+f"(a[38]), "+f"(a[39]), \
    "+f"(a[40]), "+f"(a[41]), "+f"(a[42]), "+f"(a[43]), "+f"(a[44]), "+f"(a[45]), "+f"(a[46]), "+f"(a[47]), \
    "+f"(a[48]), "+f"(a[49]), "+f"(a[50]), "+f"(a[51]), "+f"(a[52]), "+f"(a[53]), "+f"(a[54]), "+f"(a[55]), \
    "+f"(a[56]), "+f"(a[57]), "+f"(a[58]), "+f"(a[59]), "+f"(a[60]), "+f"(a[61]), "+f"(a[62]), "+f"(a[63])

#define REGS64 \
    "{%0, %1, %2, %3, %4, %5, %6, %7, %8, %9, %10, %11, %12, %13, %14, %15, " \
    "%16, %17, %18, %19, %20, %21, %22, %23, %24, %25, %26, %27, %28, %29, %30, %31, " \
    "%32, %33, %34, %35, %36, %37, %38, %39, %40, %41, %42, %43, %44, %45, %46, %47, " \
    "%48, %49, %50, %51, %52, %53, %54, %55, %56, %57, %58, %59, %60, %61, %62, %63}"

__device__ __forceinline__ void wgmma_ss(float (&d)[64], uint64_t da, uint64_t db, int scale_d) {
    asm volatile(
        "{\n.reg .pred p;\nsetp.ne.b32 p, %66, 0;\n"
        "wgmma.mma_async.sync.aligned.m64n128k16.f32.bf16.bf16 " REGS64 ", %64, %65, p, 1, 1, 0, 0;\n}\n"
        : ACC64(d) : "l"(da), "l"(db), "r"(scale_d));
}
__device__ __forceinline__ void wgmma_rs(float (&d)[64], uint32_t a0, uint32_t a1, uint32_t a2, uint32_t a3, uint64_t db, int scale_d) {
    asm volatile(
        "{\n.reg .pred p;\nsetp.ne.b32 p, %69, 0;\n"
        "wgmma.mma_async.sync.aligned.m64n128k16.f32.bf16.bf16 " REGS64 ", {%64, %65, %66, %67}, %68, p, 1, 1, 1;\n}\n"
        : ACC64(d) : "r"(a0), "r"(a1), "r"(a2), "r"(a3), "l"(db), "r"(scale_d));
}

__device__ __forceinline__ void fence_regs(float (&a)[64]) {
#pragma unroll
    for (int i = 0; i < 64; i++) asm volatile("" : "+f"(a[i])::"memory");
}
__device__ __forceinline__ void fence_regs(uint32_t (&a)[32]) {
#pragma unroll
    for (int i = 0; i < 32; i++) asm volatile("" : "+r"(a[i])::"memory");
}
__device__ __forceinline__ float ex2(float x) {
    float y;
    asm("ex2.approx.ftz.f32 %0, %1;" : "=f"(y) : "f"(x));
    return y;
}
__device__ __forceinline__ uint32_t pack_bf16(float lo, float hi) {
    uint32_t r;
    asm("cvt.rn.bf16x2.f32 %0, %1, %2;" : "=r"(r) : "f"(hi), "f"(lo));
    return r;
}

struct SoftmaxState { float m0, m1, l0, l1; };

__device__ __forceinline__ void softmax_step(float (&s)[64], SoftmaxState& st, float& a0, float& a1, float c) {
    float mx0 = fmaxf(s[0], s[1]), mx1 = fmaxf(s[2], s[3]);
#pragma unroll
    for (int n = 1; n < 16; n++) {
        mx0 = fmaxf(mx0, fmaxf(s[n * 4 + 0], s[n * 4 + 1]));
        mx1 = fmaxf(mx1, fmaxf(s[n * 4 + 2], s[n * 4 + 3]));
    }
    mx0 = fmaxf(mx0, __shfl_xor_sync(0xffffffffu, mx0, 1));
    mx1 = fmaxf(mx1, __shfl_xor_sync(0xffffffffu, mx1, 1));
    mx0 = fmaxf(mx0, __shfl_xor_sync(0xffffffffu, mx0, 2));
    mx1 = fmaxf(mx1, __shfl_xor_sync(0xffffffffu, mx1, 2));
    float mn0 = fmaxf(st.m0, mx0), mn1 = fmaxf(st.m1, mx1);
    a0 = ex2((st.m0 - mn0) * c);
    a1 = ex2((st.m1 - mn1) * c);
    st.m0 = mn0; st.m1 = mn1;
    float mc0 = mn0 * c, mc1 = mn1 * c;
    float rs0 = 0.f, rs1 = 0.f;
#pragma unroll
    for (int n = 0; n < 16; n++) {
        s[n * 4 + 0] = ex2(fmaf(s[n * 4 + 0], c, -mc0));
        s[n * 4 + 1] = ex2(fmaf(s[n * 4 + 1], c, -mc0));
        s[n * 4 + 2] = ex2(fmaf(s[n * 4 + 2], c, -mc1));
        s[n * 4 + 3] = ex2(fmaf(s[n * 4 + 3], c, -mc1));
        rs0 += s[n * 4 + 0] + s[n * 4 + 1];
        rs1 += s[n * 4 + 2] + s[n * 4 + 3];
    }
    st.l0 = st.l0 * a0 + rs0;
    st.l1 = st.l1 * a1 + rs1;
}

__device__ __forceinline__ void pack_p(const float (&s)[64], uint32_t (&p)[32]) {
#pragma unroll
    for (int i = 0; i < 32; i++) p[i] = pack_bf16(s[2 * i], s[2 * i + 1]);
}

__global__ void __launch_bounds__(384, 1)
gqa_fwd_kernel(const __grid_constant__ CUtensorMap tmQ, const __grid_constant__ CUtensorMap tmK,
               const __grid_constant__ CUtensorMap tmV, const __grid_constant__ CUtensorMap tmO,
               int nclusters) {
    extern __shared__ uint8_t smem_raw[];
    const uint32_t sbase = (smem_u32(smem_raw) + 1023u) & ~1023u;
    const uint32_t bars = sbase + SM_BAR;
    auto bar = [&](int i) { return bars + 8u * (uint32_t)i; };

    const int tid = threadIdx.x;
    const int wg = tid >> 7;
    uint32_t rank;
    asm volatile("mov.u32 %0, %%cluster_ctarank;" : "=r"(rank));
    const int cluster_id = blockIdx.x >> 1;

    if (tid == 0) {
        mbar_init(bar(B_QF + 0), 1); mbar_init(bar(B_QF + 1), 1);
        mbar_init(bar(B_QE + 0), 8); mbar_init(bar(B_QE + 1), 8);
        for (int s = 0; s < 2; s++) {
            mbar_init(bar(B_KF + s), 1); mbar_init(bar(B_KE + s), 16);
            mbar_init(bar(B_VF + s), 1); mbar_init(bar(B_VE + s), 16);
        }
        asm volatile("fence.mbarrier_init.release.cluster;" ::: "memory");
    }
    __syncthreads();
    asm volatile("barrier.cluster.arrive.release.aligned;" ::: "memory");
    asm volatile("barrier.cluster.wait.acquire.aligned;" ::: "memory");

    const int ntiles = (NUNITS - cluster_id + nclusters - 1) / nclusters;

    if (wg == 0) {
        asm volatile("setmaxnreg.dec.sync.aligned.u32 24;");
        if (tid == 0) {
            uint32_t kv = 0;
            for (int it = 0; it < ntiles; it++) {
                const int u = cluster_id + it * nclusters;
                const int g = u >> 2, qd = u & 3;
                const uint32_t qs = it & 1;
                mbar_wait(bar(B_QE + qs), ((it >> 1) & 1) ^ 1);
                mbar_expect_tx(bar(B_QF + qs), TILE_BYTES);
                const int qrow = qd * 256 + (int)rank * 128;
                tma_load_3d(sbase + SM_Q + qs * TILE_BYTES, &tmQ, bar(B_QF + qs), 0, qrow, g);
                tma_load_3d(sbase + SM_Q + qs * TILE_BYTES + 16384, &tmQ, bar(B_QF + qs), 64, qrow, g);
                for (int j = 0; j < NBLK; j++, kv++) {
                    const uint32_t s = kv & 1, ph = ((kv >> 1) & 1) ^ 1;
                    const int krow = g * SK + j * 128 + (int)rank * 64;
                    mbar_wait_cluster(bar(B_KE + s), ph);
                    mbar_expect_tx(bar(B_KF + s), TILE_BYTES);
                    tma_load_2d_mc(sbase + SM_K + s * TILE_BYTES + rank * 8192, &tmK, bar(B_KF + s), 0, krow, 3);
                    tma_load_2d_mc(sbase + SM_K + s * TILE_BYTES + 16384 + rank * 8192, &tmK, bar(B_KF + s), 64, krow, 3);
                    mbar_wait_cluster(bar(B_VE + s), ph);
                    mbar_expect_tx(bar(B_VF + s), TILE_BYTES);
                    tma_load_2d_mc(sbase + SM_V + s * TILE_BYTES + rank * 8192, &tmV, bar(B_VF + s), 0, krow, 3);
                    tma_load_2d_mc(sbase + SM_V + s * TILE_BYTES + 16384 + rank * 8192, &tmV, bar(B_VF + s), 64, krow, 3);
                }
            }
        }
    } else {
        asm volatile("setmaxnreg.inc.sync.aligned.u32 240;");
        const int cw = wg - 1;
        const int lane = tid & 31;
        const int warp = (tid >> 5) & 3;
        const uint32_t peer = rank ^ 1u;
        const float c = 0.08838834764831845f * 1.4426950408889634f;

        float o[64], s[64];
        uint32_t p[32];
        SoftmaxState st;
        st.m0 = st.m1 = -INFINITY; st.l0 = st.l1 = 0.f;

        if (cw == 1) bar_arrive(1, 256);

        const int T = ntiles * NBLK;
        auto issue_qk = [&](uint32_t qs, uint32_t ks) {
            const uint32_t qa = sbase + SM_Q + qs * TILE_BYTES + cw * 8192;
            const uint32_t ka = sbase + SM_K + ks * TILE_BYTES;
#pragma unroll
            for (int kk = 0; kk < 8; kk++) {
                const uint32_t off = (kk >> 2) * 16384 + (kk & 3) * 32;
                wgmma_ss(s, make_desc(qa + off, 16, 1024), make_desc(ka + off, 16, 1024), kk != 0);
            }
        };
        auto release = [&](int b) {
            if (lane == 0) { mbar_arrive(bar(b)); mbar_arrive_remote(bar(b), peer); }
        };

        mbar_wait(bar(B_QF + 0), 0);
        mbar_wait(bar(B_KF + 0), 0);
        bar_sync(1 + cw, 256);
        wgmma_fence();
        issue_qk(0, 0);
        wgmma_commit();
        bar_arrive(2 - cw, 256);
        wgmma_wait<0>();
        fence_regs(s);
        release(B_KE + 0);
        {
            float a0, a1;
            softmax_step(s, st, a0, a1, c);
            pack_p(s, p);
        }

        for (int t = 0; t < T; t++) {
            const int j = t & 3;
            const int it = t >> 2;
            const bool has_next = (t + 1 < T);
            const uint32_t vs = t & 1;
            const uint32_t ksn = (t + 1) & 1;
            const uint32_t qsn = ((t + 1) >> 2) & 1;
            if (has_next) {
                if (j == 3) mbar_wait(bar(B_QF + qsn), ((it + 1) >> 1) & 1);
                mbar_wait(bar(B_KF + ksn), ((t + 1) >> 1) & 1);
            }
            mbar_wait(bar(B_VF + vs), (t >> 1) & 1);
            bar_sync(1 + cw, 256);
            wgmma_fence();
            if (has_next) {
                issue_qk(qsn, ksn);
                wgmma_commit();
            }
            {
                const uint32_t va = sbase + SM_V + vs * TILE_BYTES;
#pragma unroll
                for (int kk = 0; kk < 8; kk++) {
                    wgmma_rs(o, p[4 * kk], p[4 * kk + 1], p[4 * kk + 2], p[4 * kk + 3],
                             make_desc(va + kk * 2048, 16384, 1024), (kk != 0) | (j != 0));
                }
                wgmma_commit();
            }
            bar_arrive(2 - cw, 256);
            float lf0 = st.l0, lf1 = st.l1;
            float a0 = 1.f, a1 = 1.f;
            if (has_next) {
                wgmma_wait<1>();
                fence_regs(s);
                release(B_KE + ksn);
                if (j == 3) {
                    st.m0 = st.m1 = -INFINITY; st.l0 = st.l1 = 0.f;
                }
                if (j == 2) { if (lane == 0) mbar_arrive(bar(B_QE + (it & 1))); }
                softmax_step(s, st, a0, a1, c);
            }
            wgmma_wait<0>();
            fence_regs(o);
            fence_regs(p);
            release(B_VE + vs);
            if (j == 3) {
                lf0 += __shfl_xor_sync(0xffffffffu, lf0, 1);
                lf1 += __shfl_xor_sync(0xffffffffu, lf1, 1);
                lf0 += __shfl_xor_sync(0xffffffffu, lf0, 2);
                lf1 += __shfl_xor_sync(0xffffffffu, lf1, 2);
                const float i0 = 1.f / lf0, i1 = 1.f / lf1;
                if ((tid & 127) == 0) asm volatile("cp.async.bulk.wait_group.read 0;" ::: "memory");
                bar_sync(3 + cw, 128);
                const uint32_t ob = sbase + SM_O + cw * 16384;
                const int r0 = warp * 16 + (lane >> 2);
#pragma unroll
                for (int n = 0; n < 16; n++) {
                    const uint32_t half = n >> 3, ch = n & 7;
                    const uint32_t a_lo = ob + half * 8192 + r0 * 128 + ((ch ^ (r0 & 7)) << 4) + (lane & 3) * 4;
                    const uint32_t a_hi = a_lo + 8 * 128;
                    const uint32_t v0 = pack_bf16(o[n * 4 + 0] * i0, o[n * 4 + 1] * i0);
                    const uint32_t v1 = pack_bf16(o[n * 4 + 2] * i1, o[n * 4 + 3] * i1);
                    asm volatile("st.shared.b32 [%0], %1;" ::"r"(a_lo), "r"(v0) : "memory");
                    asm volatile("st.shared.b32 [%0], %1;" ::"r"(a_hi), "r"(v1) : "memory");
                }
                asm volatile("fence.proxy.async.shared::cta;" ::: "memory");
                bar_sync(3 + cw, 128);
                if ((tid & 127) == 0) {
                    const int u = cluster_id + it * nclusters;
                    const int g = u >> 2, qd = u & 3;
                    const int orow = qd * 256 + (int)rank * 128 + cw * 64;
                    tma_store_3d(&tmO, ob, 0, orow, g);
                    tma_store_3d(&tmO, ob + 8192, 64, orow, g);
                    asm volatile("cp.async.bulk.commit_group;" ::: "memory");
                }
            } else {
#pragma unroll
                for (int n = 0; n < 16; n++) {
                    o[n * 4 + 0] *= a0; o[n * 4 + 1] *= a0;
                    o[n * 4 + 2] *= a1; o[n * 4 + 3] *= a1;
                }
            }
            if (has_next) pack_p(s, p);
        }
        if ((tid & 127) == 0) asm volatile("cp.async.bulk.wait_group 0;" ::: "memory");
    }
    asm volatile("barrier.cluster.arrive.release.aligned;" ::: "memory");
    asm volatile("barrier.cluster.wait.acquire.aligned;" ::: "memory");
}

typedef CUresult (*PFN_encodeTiled)(CUtensorMap*, CUtensorMapDataType, cuuint32_t, void*, const cuuint64_t*,
                                    const cuuint64_t*, const cuuint32_t*, const cuuint32_t*, CUtensorMapInterleave,
                                    CUtensorMapSwizzle, CUtensorMapL2promotion, CUtensorMapFloatOOBfill);

}

extern "C" void kernel_launch(void* const* d_in, const int* in_sizes, int n_in, void* d_out, int out_size) {
    static PFN_encodeTiled encode = nullptr;
    static int nclusters = 0;
    if (!encode) {
        void* fn = nullptr;
        cudaDriverEntryPointQueryResult qres;
        cudaGetDriverEntryPoint("cuTensorMapEncodeTiled", &fn, cudaEnableDefault, &qres);
        encode = (PFN_encodeTiled)fn;
        cudaFuncSetAttribute(gqa_fwd_kernel, cudaFuncAttributeMaxDynamicSharedMemorySize, SMEM_BYTES);
        cudaLaunchConfig_t cfg = {};
        cfg.gridDim = dim3(132, 1, 1);
        cfg.blockDim = dim3(384, 1, 1);
        cfg.dynamicSmemBytes = SMEM_BYTES;
        cudaLaunchAttribute attr[1];
        attr[0].id = cudaLaunchAttributeClusterDimension;
        attr[0].val.clusterDim.x = 2; attr[0].val.clusterDim.y = 1; attr[0].val.clusterDim.z = 1;
        cfg.attrs = attr; cfg.numAttrs = 1;
        int nc = 0;
        if (cudaOccupancyMaxActiveClusters(&nc, gqa_fwd_kernel, &cfg) != cudaSuccess || nc <= 0) nc = 64;
        nclusters = nc;
    }
    CUtensorMap tmQ, tmK, tmV, tmO;
    {
        cuuint64_t dims[3] = {HD, GROWS, GROUPS};
        cuuint64_t strides[2] = {HD * 2, (cuuint64_t)GROWS * HD * 2};
        cuuint32_t estr[3] = {1, 1, 1};
        cuuint32_t boxq[3] = {64, 128, 1};
        encode(&tmQ, CU_TENSOR_MAP_DATA_TYPE_BFLOAT16, 3, d_in[0], dims, strides, boxq, estr,
               CU_TENSOR_MAP_INTERLEAVE_NONE, CU_TENSOR_MAP_SWIZZLE_128B, CU_TENSOR_MAP_L2_PROMOTION_L2_128B,
               CU_TENSOR_MAP_FLOAT_OOB_FILL_NONE);
        cuuint32_t boxo[3] = {64, 64, 1};
        encode(&tmO, CU_TENSOR_MAP_DATA_TYPE_BFLOAT16, 3, d_out, dims, strides, boxo, estr,
               CU_TENSOR_MAP_INTERLEAVE_NONE, CU_TENSOR_MAP_SWIZZLE_128B, CU_TENSOR_MAP_L2_PROMOTION_L2_128B,
               CU_TENSOR_MAP_FLOAT_OOB_FILL_NONE);
    }
    {
        cuuint64_t dims[2] = {HD, (cuuint64_t)GROUPS * SK};
        cuuint64_t strides[1] = {HD * 2};
        cuuint32_t estr[2] = {1, 1};
        cuuint32_t box[2] = {64, 64};
        encode(&tmK, CU_TENSOR_MAP_DATA_TYPE_BFLOAT16, 2, d_in[1], dims, strides, box, estr,
               CU_TENSOR_MAP_INTERLEAVE_NONE, CU_TENSOR_MAP_SWIZZLE_128B, CU_TENSOR_MAP_L2_PROMOTION_L2_128B,
               CU_TENSOR_MAP_FLOAT_OOB_FILL_NONE);
        encode(&tmV, CU_TENSOR_MAP_DATA_TYPE_BFLOAT16, 2, d_in[2], dims, strides, box, estr,
               CU_TENSOR_MAP_INTERLEAVE_NONE, CU_TENSOR_MAP_SWIZZLE_128B, CU_TENSOR_MAP_L2_PROMOTION_L2_128B,
               CU_TENSOR_MAP_FLOAT_OOB_FILL_NONE);
    }
    cudaLaunchConfig_t cfg = {};
    cfg.gridDim = dim3(2 * nclusters, 1, 1);
    cfg.blockDim = dim3(384, 1, 1);
    cfg.dynamicSmemBytes = SMEM_BYTES;
    cfg.stream = cudaStreamPerThread;
    cudaLaunchAttribute attr[1];
    attr[0].id = cudaLaunchAttributeClusterDimension;
    attr[0].val.clusterDim.x = 2; attr[0].val.clusterDim.y = 1; attr[0].val.clusterDim.z = 1;
    cfg.attrs = attr; cfg.numAttrs = 1;
    cudaLaunchKernelEx(&cfg, gqa_fwd_kernel, tmQ, tmK, tmV, tmO, nclusters);
}
```

```cpp
#include <cuda_runtime.h>
#include <cuda_bf16.h>
#include <cuda.h>
#include <stdint.h>
#include <type_traits>

__device__ int g_tail_claims;

namespace {

constexpr int HD      = 128;
constexpr int SQ      = 496;
constexpr int SK      = 512;
constexpr int HQ      = 32;
constexpr int HKV     = 16;
constexpr int BATCH   = 16;
constexpr int GROUPS  = BATCH * HKV;
constexpr int GROWS   = SQ * (HQ / HKV);
constexpr int UNITS_PER_GROUP = 4;
constexpr int NUNITS  = GROUPS * UNITS_PER_GROUP;
constexpr int NBLK    = SK / 128;

constexpr uint32_t TILE_BYTES = 128 * 128 * 2;
constexpr uint32_t SM_Q = 0;
constexpr uint32_t SM_K = 2 * TILE_BYTES;
constexpr uint32_t SM_V = 4 * TILE_BYTES;
constexpr uint32_t SM_BAR = 7 * TILE_BYTES;
constexpr uint32_t SMEM_BYTES = SM_BAR + 256 + 1024;

enum { B_QF = 0, B_QE = 2, B_KF = 4, B_KE = 6, B_VF = 8, B_VE = 11, B_OF = 14, B_TL = 16, B_NUM = 17 };

__device__ __forceinline__ uint32_t smem_u32(const void* p) {
    return (uint32_t)__cvta_generic_to_shared(p);
}
__device__ __forceinline__ void mbar_init(uint32_t bar, uint32_t cnt) {
    asm volatile("mbarrier.init.shared::cta.b64 [%0], %1;" ::"r"(bar), "r"(cnt) : "memory");
}
__device__ __forceinline__ void mbar_expect_tx(uint32_t bar, uint32_t bytes) {
    asm volatile("mbarrier.arrive.expect_tx.shared::cta.b64 _, [%0], %1;" ::"r"(bar), "r"(bytes) : "memory");
}
__device__ __forceinline__ void mbar_arrive(uint32_t bar) {
    asm volatile("mbarrier.arrive.shared::cta.b64 _, [%0];" ::"r"(bar) : "memory");
}
__device__ __forceinline__ void mbar_arrive_remote(uint32_t bar, uint32_t cta) {
    asm volatile(
        "{\n.reg .b32 ra;\n"
        "mapa.shared::cluster.u32 ra, %0, %1;\n"
        "mbarrier.arrive.shared::cluster.b64 _, [ra];\n}\n" ::"r"(bar), "r"(cta) : "memory");
}
__device__ __forceinline__ void mbar_wait(uint32_t bar, uint32_t parity) {
    asm volatile(
        "{\n.reg .pred p;\n.reg .u32 n;\n"
        "mov.u32 n, 0;\n"
        "WAIT_LOOP:\n"
        "mbarrier.try_wait.parity.shared::cta.b64 p, [%0], %1;\n"
        "@p bra WAIT_DONE;\n"
        "add.u32 n, n, 1;\n"
        "setp.gt.u32 p, n, 4194304;\n"
        "@p trap;\n"
        "bra WAIT_LOOP;\n"
        "WAIT_DONE:\n}\n" ::"r"(bar), "r"(parity) : "memory");
}
__device__ __forceinline__ void publish_cluster(uint32_t slot, uint32_t bar, uint32_t cta, int val) {
    asm volatile(
        "{\n.reg .b32 rs, rb;\n"
        "mapa.shared::cluster.u32 rs, %0, %2;\n"
        "mapa.shared::cluster.u32 rb, %1, %2;\n"
        "st.shared::cluster.b32 [rs], %3;\n"
        "mbarrier.arrive.release.cluster.shared::cluster.b64 _, [rb];\n}\n" ::"r"(slot), "r"(bar), "r"(cta), "r"(val) : "memory");
}
__device__ __forceinline__ int read_published(uint32_t slot, uint32_t bar) {
    asm volatile(
        "{\n.reg .pred p;\n.reg .u32 n;\n"
        "mov.u32 n, 0;\n"
        "WAIT_LOOP:\n"
        "mbarrier.try_wait.parity.acquire.cluster.shared::cta.b64 p, [%0], 0;\n"
        "@p bra WAIT_DONE;\n"
        "add.u32 n, n, 1;\n"
        "setp.gt.u32 p, n, 4194304;\n"
        "@p trap;\n"
        "bra WAIT_LOOP;\n"
        "WAIT_DONE:\n}\n" ::"r"(bar) : "memory");
    int v;
    asm volatile("ld.shared.b32 %0, [%1];" : "=r"(v) : "r"(slot) : "memory");
    return v;
}
__device__ __forceinline__ uint32_t mbar_test(uint32_t bar, uint32_t parity) {
    uint32_t ok;
    asm volatile(
        "{\n.reg .pred p;\n"
        "mbarrier.test_wait.parity.shared::cta.b64 p, [%1], %2;\n"
        "selp.u32 %0, 1, 0, p;\n}\n" : "=r"(ok) : "r"(bar), "r"(parity) : "memory");
    return ok;
}
__device__ __forceinline__ void tma_load_3d(uint32_t dst, const CUtensorMap* map, uint32_t bar, int c0, int c1, int c2) {
    asm volatile(
        "cp.async.bulk.tensor.3d.shared::cluster.global.mbarrier::complete_tx::bytes [%0], [%1, {%3, %4, %5}], [%2];"
        ::"r"(dst), "l"(map), "r"(bar), "r"(c0), "r"(c1), "r"(c2) : "memory");
}
__device__ __forceinline__ void tma_load_2d_mc(uint32_t dst, const CUtensorMap* map, uint32_t bar, int c0, int c1, uint16_t mask) {
    asm volatile(
        "cp.async.bulk.tensor.2d.shared::cluster.global.mbarrier::complete_tx::bytes.multicast::cluster [%0], [%1, {%3, %4}], [%2], %5;"
        ::"r"(dst), "l"(map), "r"(bar), "r"(c0), "r"(c1), "h"(mask) : "memory");
}
__device__ __forceinline__ void tma_prefetch_2d(const CUtensorMap* map, int c0, int c1) {
    asm volatile("cp.async.bulk.prefetch.tensor.2d.L2.global [%0, {%1, %2}];" ::"l"(map), "r"(c0), "r"(c1) : "memory");
}
__device__ __forceinline__ void tma_store_3d(const CUtensorMap* map, uint32_t src, int c0, int c1, int c2) {
    asm volatile(
        "cp.async.bulk.tensor.3d.global.shared::cta.bulk_group [%0, {%2, %3, %4}], [%1];"
        ::"l"(map), "r"(src), "r"(c0), "r"(c1), "r"(c2) : "memory");
}
__device__ __forceinline__ void bar_sync(int id, int n) { asm volatile("bar.sync %0, %1;" ::"r"(id), "r"(n) : "memory"); }
__device__ __forceinline__ void bar_arrive(int id, int n) { asm volatile("bar.arrive %0, %1;" ::"r"(id), "r"(n) : "memory"); }

__device__ __forceinline__ void wgmma_fence() { asm volatile("wgmma.fence.sync.aligned;" ::: "memory"); }
__device__ __forceinline__ void wgmma_commit() { asm volatile("wgmma.commit_group.sync.aligned;" ::: "memory"); }
template <int N> __device__ __forceinline__ void wgmma_wait() { asm volatile("wgmma.wait_group.sync.aligned %0;" ::"n"(N) : "memory"); }

__device__ __forceinline__ uint32_t desc_lo(uint32_t addr, uint32_t lbo) {
    return ((addr & 0x3FFFF) >> 4) | ((lbo >> 4) << 16);
}
__device__ __forceinline__ uint64_t desc_from_lo(uint32_t lo) {
    uint64_t d;
    asm("mov.b64 %0, {%1, %2};" : "=l"(d) : "r"(lo), "r"(0x40000040u));
    return d;
}

#define ACC64(a) \
    "+f"(a[0]), "+f"(a[1]), "+f"(a[2]), "+f"(a[3]), "+f"(a[4]), "+f"(a[5]), "+f"(a[6]), "+f"(a[7]), \
    "+f"(a[8]), "+f"(a[9]), "+f"(a[10]), "+f"(a[11]), "+f"(a[12]), "+f"(a[13]), "+f"(a[14]), "+f"(a[15]), \
    "+f"(a[16]), "+f"(a[17]), "+f"(a[18]), "+f"(a[19]), "+f"(a[20]), "+f"(a[21]), "+f"(a[22]), "+f"(a[23]), \
    "+f"(a[24]), "+f"(a[25]), "+f"(a[26]), "+f"(a[27]), "+f"(a[28]), "+f"(a[29]), "+f"(a[30]), "+f"(a[31]), \
    "+f"(a[32]), "+f"(a[33]), "+f"(a[34]), "+f"(a[35]), "+f"(a[36]), "+f"(a[37]), "+f"(a[38]), "+f"(a[39]), \
    "+f"(a[40]), "+f"(a[41]), "+f"(a[42]), "+f"(a[43]), "+f"(a[44]), "+f"(a[45]), "+f"(a[46]), "+f"(a[47]), \
    "+f"(a[48]), "+f"(a[49]), "+f"(a[50]), "+f"(a[51]), "+f"(a[52]), "+f"(a[53]), "+f"(a[54]), "+f"(a[55]), \
    "+f"(a[56]), "+f"(a[57]), "+f"(a[58]), "+f"(a[59]), "+f"(a[60]), "+f"(a[61]), "+f"(a[62]), "+f"(a[63])

#define REGS64 \
    "{%0, %1, %2, %3, %4, %5, %6, %7, %8, %9, %10, %11, %12, %13, %14, %15, " \
    "%16, %17, %18, %19, %20, %21, %22, %23, %24, %25, %26, %27, %28, %29, %30, %31, " \
    "%32, %33, %34, %35, %36, %37, %38, %39, %40, %41, %42, %43, %44, %45, %46, %47, " \
    "%48, %49, %50, %51, %52, %53, %54, %55, %56, %57, %58, %59, %60, %61, %62, %63}"

__device__ __forceinline__ void wgmma_ss(float (&d)[64], uint64_t da, uint64_t db, int scale_d) {
    asm volatile(
        "{\n.reg .pred p;\nsetp.ne.b32 p, %66, 0;\n"
        "wgmma.mma_async.sync.aligned.m64n128k16.f32.bf16.bf16 " REGS64 ", %64, %65, p, 1, 1, 0, 0;\n}\n"
        : ACC64(d) : "l"(da), "l"(db), "r"(scale_d));
}
__device__ __forceinline__ void wgmma_rs(float (&d)[64], uint32_t a0, uint32_t a1, uint32_t a2, uint32_t a3, uint64_t db, int scale_d) {
    asm volatile(
        "{\n.reg .pred p;\nsetp.ne.b32 p, %69, 0;\n"
        "wgmma.mma_async.sync.aligned.m64n128k16.f32.bf16.bf16 " REGS64 ", {%64, %65, %66, %67}, %68, p, 1, 1, 1;\n}\n"
        : ACC64(d) : "r"(a0), "r"(a1), "r"(a2), "r"(a3), "l"(db), "r"(scale_d));
}

__device__ __forceinline__ void fence_regs(float (&a)[64]) {
#pragma unroll
    for (int i = 0; i < 64; i++) asm volatile("" : "+f"(a[i])::"memory");
}
__device__ __forceinline__ void fence_regs(uint32_t (&a)[32]) {
#pragma unroll
    for (int i = 0; i < 32; i++) asm volatile("" : "+r"(a[i])::"memory");
}
__device__ __forceinline__ float ex2(float x) {
    float y;
    asm volatile("ex2.approx.ftz.f32 %0, %1;" : "=f"(y) : "f"(x));
    return y;
}
__device__ __forceinline__ uint32_t pack_bf16(float lo, float hi) {
    uint32_t r;
    asm("cvt.rn.bf16x2.f32 %0, %1, %2;" : "=r"(r) : "f"(hi), "f"(lo));
    return r;
}

__device__ __forceinline__ void stmatrix_x4(uint32_t addr, uint32_t r0, uint32_t r1, uint32_t r2, uint32_t r3) {
    asm volatile("stmatrix.sync.aligned.m8n8.x4.shared.b16 [%0], {%1, %2, %3, %4};"
                 ::"r"(addr), "r"(r0), "r"(r1), "r"(r2), "r"(r3) : "memory");
}

__device__ __forceinline__ void block_max(const float (&s)[64], float& mx0, float& mx1) {
    float a0 = fmaxf(s[0], s[1]), a1 = fmaxf(s[2], s[3]);
    float b0 = fmaxf(s[4], s[5]), b1 = fmaxf(s[6], s[7]);
#pragma unroll
    for (int n = 2; n < 16; n += 2) {
        a0 = fmaxf(a0, fmaxf(s[n * 4 + 0], s[n * 4 + 1]));
        a1 = fmaxf(a1, fmaxf(s[n * 4 + 2], s[n * 4 + 3]));
        b0 = fmaxf(b0, fmaxf(s[n * 4 + 4], s[n * 4 + 5]));
        b1 = fmaxf(b1, fmaxf(s[n * 4 + 6], s[n * 4 + 7]));
    }
    mx0 = fmaxf(a0, b0); mx1 = fmaxf(a1, b1);
    mx0 = fmaxf(mx0, __shfl_xor_sync(0xffffffffu, mx0, 1));
    mx1 = fmaxf(mx1, __shfl_xor_sync(0xffffffffu, mx1, 1));
    mx0 = fmaxf(mx0, __shfl_xor_sync(0xffffffffu, mx0, 2));
    mx1 = fmaxf(mx1, __shfl_xor_sync(0xffffffffu, mx1, 2));
}

__device__ __forceinline__ void scale_shift(float (&s)[64], float c, float mc0, float mc1) {
#pragma unroll
    for (int n = 0; n < 16; n++) {
        s[n * 4 + 0] = fmaf(s[n * 4 + 0], c, -mc0);
        s[n * 4 + 1] = fmaf(s[n * 4 + 1], c, -mc0);
        s[n * 4 + 2] = fmaf(s[n * 4 + 2], c, -mc1);
        s[n * 4 + 3] = fmaf(s[n * 4 + 3], c, -mc1);
    }
}
__device__ __forceinline__ void exp_pack(const float (&x)[64], uint32_t (&p)[32], float& rs0, float& rs1) {
    float r0 = 0.f, r1 = 0.f, r2 = 0.f, r3 = 0.f;
#pragma unroll
    for (int n = 0; n < 16; n++) {
        const float e0 = ex2(x[n * 4 + 0]);
        const float e1 = ex2(x[n * 4 + 1]);
        const float e2 = ex2(x[n * 4 + 2]);
        const float e3 = ex2(x[n * 4 + 3]);
        r0 += e0; r1 += e1; r2 += e2; r3 += e3;
        p[2 * n] = pack_bf16(e0, e1);
        p[2 * n + 1] = pack_bf16(e2, e3);
    }
    rs0 = r0 + r1; rs1 = r2 + r3;
}

__global__ void __launch_bounds__(384, 1)
gqa_fwd_kernel(const __grid_constant__ CUtensorMap tmQ, const __grid_constant__ CUtensorMap tmK,
               const __grid_constant__ CUtensorMap tmV, const __grid_constant__ CUtensorMap tmO,
               int nclusters) {
    extern __shared__ uint8_t smem_raw[];
    const uint32_t sbase = (smem_u32(smem_raw) + 1023u) & ~1023u;
    const uint32_t bars = sbase + SM_BAR;
    auto bar = [&](int i) { return bars + 8u * (uint32_t)i; };

    const int tid = threadIdx.x;
    const int wg = __shfl_sync(0xffffffffu, tid >> 7, 0);
    uint32_t rank;
    asm volatile("mov.u32 %0, %%cluster_ctarank;" : "=r"(rank));
    const int cluster_id = blockIdx.x >> 1;

    if (tid == 0) {
        mbar_init(bar(B_QF + 0), 1); mbar_init(bar(B_QF + 1), 1);
        mbar_init(bar(B_QE + 0), 1); mbar_init(bar(B_QE + 1), 1);
        mbar_init(bar(B_OF + 0), 4); mbar_init(bar(B_OF + 1), 4);
        mbar_init(bar(B_TL), 1);
        for (int s = 0; s < 2; s++) { mbar_init(bar(B_KF + s), 1); mbar_init(bar(B_KE + s), 16); }
        for (int s = 0; s < 3; s++) { mbar_init(bar(B_VF + s), 1); mbar_init(bar(B_VE + s), 16); }
        asm volatile("fence.mbarrier_init.release.cluster;" ::: "memory");
    }
    __syncthreads();
    asm volatile("barrier.cluster.arrive.release.aligned;" ::: "memory");
    asm volatile("barrier.cluster.wait.acquire.aligned;" ::: "memory");

    const int nstatic = NUNITS / nclusters;
    const int ntail = NUNITS - nstatic * nclusters;
    const uint32_t tail_slot = bars + 8u * B_NUM;
    int tail_unit = -1;
    int ntiles = nstatic;
    auto unit_of = [&](int it) { return it < nstatic ? cluster_id + it * nclusters : tail_unit; };
    auto fetch_tail = [&]() {
        tail_unit = read_published(tail_slot, bar(B_TL));
        ntiles = nstatic + (tail_unit >= 0 ? 1 : 0);
    };

    if (wg == 0) {
        asm volatile("setmaxnreg.dec.sync.aligned.u32 24;");
        if (tid == 0) {
            int T = ntiles * NBLK;
            auto load_q = [&](int it) {
                const int u = unit_of(it);
                const int g = u >> 2, qd = u & 3;
                const uint32_t qs = it & 1;
                mbar_wait(bar(B_QE + qs), ((it >> 1) & 1) ^ 1);
                mbar_expect_tx(bar(B_QF + qs), TILE_BYTES);
                const int qrow = qd * 256 + (int)rank * 128;
                tma_load_3d(sbase + SM_Q + qs * TILE_BYTES, &tmQ, bar(B_QF + qs), 0, qrow, g);
                tma_load_3d(sbase + SM_Q + qs * TILE_BYTES + 16384, &tmQ, bar(B_QF + qs), 64, qrow, g);
            };
            auto load_kv = [&](int t, uint32_t s, uint32_t ph, const CUtensorMap* map, uint32_t smem_off, int bfull, int bempty) {
                const int u = unit_of(t >> 2);
                const int krow = (u >> 2) * SK + (t & 3) * 128 + (int)rank * 64;
                mbar_wait(bar(bempty + s), ph);
                mbar_expect_tx(bar(bfull + s), TILE_BYTES);
                tma_load_2d_mc(sbase + smem_off + s * TILE_BYTES + rank * 8192, map, bar(bfull + s), 0, krow, 3);
                tma_load_2d_mc(sbase + smem_off + s * TILE_BYTES + 16384 + rank * 8192, map, bar(bfull + s), 64, krow, 3);
            };
            auto prefetch_kv = [&](int t) {
                const int u = unit_of(t >> 2);
                const int krow = (u >> 2) * SK + (t & 3) * 128 + (int)rank * 64;
                tma_prefetch_2d(&tmK, 0, krow); tma_prefetch_2d(&tmK, 64, krow);
                tma_prefetch_2d(&tmV, 0, krow); tma_prefetch_2d(&tmV, 64, krow);
            };
            load_q(0);
            load_kv(0, 0, 1, &tmK, SM_K, B_KF, B_KE);
            for (int t = 1; t < 4; t++) prefetch_kv(t);
            uint32_t vs = 0, vph = 1;
            for (int t = 0; t < T; t++) {
                if (t == 4 * (nstatic - 2)) {
                    if (rank == 0) {
                        const int idx = atomicAdd(&g_tail_claims, 1);
                        if (idx == nclusters - 1) atomicExch(&g_tail_claims, 0);
                        const int val = idx < ntail ? nstatic * nclusters + idx : -1;
                        publish_cluster(tail_slot, bar(B_TL), 0, val);
                        publish_cluster(tail_slot, bar(B_TL), 1, val);
                    }
                    fetch_tail();
                    T = ntiles * NBLK;
                }
                if (t + 4 < T && ((t ^ unit_of((t >> 2) + 1)) & 1) == 0) prefetch_kv(t + 4);
                if (t + 1 < T) load_kv(t + 1, (t + 1) & 1, (((t + 1) >> 1) & 1) ^ 1, &tmK, SM_K, B_KF, B_KE);
                load_kv(t, vs, vph, &tmV, SM_V, B_VF, B_VE);
                if (++vs == 3) { vs = 0; vph ^= 1; }
                if (t == 0 && ntiles > 1) load_q(1);
            }
        }
        if (tid == 32) {
            for (int it = 0; it < ntiles; it++) {
                if (it == nstatic - 2) fetch_tail();
                const int u = unit_of(it);
                const int g = u >> 2, qd = u & 3;
                const int orow = qd * 256 + (int)rank * 128;
                const uint32_t ob = sbase + SM_Q + (it & 1) * TILE_BYTES;
#pragma unroll
                for (int w = 0; w < 2; w++) {
                    mbar_wait(bar(B_OF + w), it & 1);
                    tma_store_3d(&tmO, ob + w * 8192, 0, orow + w * 64, g);
                    tma_store_3d(&tmO, ob + 16384 + w * 8192, 64, orow + w * 64, g);
                    asm volatile("cp.async.bulk.commit_group;" ::: "memory");
                }
                asm volatile("cp.async.bulk.wait_group.read 0;" ::: "memory");
                if (it + 2 < ntiles) {
                    const int u2 = unit_of(it + 2);
                    const int qrow = (u2 & 3) * 256 + (int)rank * 128;
                    mbar_expect_tx(bar(B_QF + (it & 1)), TILE_BYTES);
                    tma_load_3d(ob, &tmQ, bar(B_QF + (it & 1)), 0, qrow, u2 >> 2);
                    tma_load_3d(ob + 16384, &tmQ, bar(B_QF + (it & 1)), 64, qrow, u2 >> 2);
                }
            }
            asm volatile("cp.async.bulk.wait_group 0;" ::: "memory");
        }
        __syncwarp();
        asm volatile("barrier.cluster.arrive.release.aligned;" ::: "memory");
        asm volatile("barrier.cluster.wait.acquire.aligned;" ::: "memory");
    } else {
        asm volatile("setmaxnreg.inc.sync.aligned.u32 240;");
        const int cw = wg - 1;
        const int lane = tid & 31;
        const int warp = (tid >> 5) & 3;
        const uint32_t peer = rank ^ 1u;
        const float c = 0.08838834764831845f * 1.4426950408889634f;

        float o[64], s[64];
        uint32_t pa[32], pb[32];
        float mref0, mref1, l0, l1;

        if (cw == 1) bar_arrive(1, 256);

        const uint32_t q_lo = desc_lo(sbase + SM_Q + cw * 8192, 16);
        const uint32_t k_lo = desc_lo(sbase + SM_K, 16);
        const uint32_t v_lo = desc_lo(sbase + SM_V, 16384);
        auto issue_qk = [&](uint32_t qs, uint32_t ks) {
            const uint32_t qa = q_lo + qs * (TILE_BYTES >> 4);
            const uint32_t ka = k_lo + ks * (TILE_BYTES >> 4);
#pragma unroll
            for (int kk = 0; kk < 8; kk++) {
                const uint32_t off = ((kk >> 2) * 16384 + (kk & 3) * 32) >> 4;
                wgmma_ss(s, desc_from_lo(qa + off), desc_from_lo(ka + off), kk != 0);
            }
        };
        auto issue_pv = [&](uint32_t (&p)[32], uint32_t vs, int acc) {
            const uint32_t va = v_lo + vs * (TILE_BYTES >> 4);
#pragma unroll
            for (int kk = 0; kk < 8; kk++) {
                wgmma_rs(o, p[4 * kk], p[4 * kk + 1], p[4 * kk + 2], p[4 * kk + 3],
                         desc_from_lo(va + kk * (2048 >> 4)), (kk != 0) | acc);
            }
        };
        auto release = [&](int b) {
            if (lane == 0) { mbar_arrive(bar(b)); mbar_arrive_remote(bar(b), peer); }
        };
        auto epilogue = [&](int it, float lf0, float lf1) {
            lf0 += __shfl_xor_sync(0xffffffffu, lf0, 1);
            lf1 += __shfl_xor_sync(0xffffffffu, lf1, 1);
            lf0 += __shfl_xor_sync(0xffffffffu, lf0, 2);
            lf1 += __shfl_xor_sync(0xffffffffu, lf1, 2);
            const float i0 = 1.f / lf0, i1 = 1.f / lf1;
            const uint32_t ob = sbase + SM_Q + (it & 1) * TILE_BYTES + cw * 8192;
            const uint32_t row = warp * 16 + ((lane >> 3) & 1) * 8 + (lane & 7);
            const uint32_t rbase = ob + row * 128;
            const uint32_t csel = lane >> 4;
#pragma unroll
            for (int n = 0; n < 16; n += 2) {
                const uint32_t half = n >> 3, ch = (n & 7) + csel;
                const uint32_t addr = rbase + half * 16384 + ((ch ^ (row & 7)) << 4);
                stmatrix_x4(addr,
                            pack_bf16(o[n * 4 + 0] * i0, o[n * 4 + 1] * i0), pack_bf16(o[n * 4 + 2] * i1, o[n * 4 + 3] * i1),
                            pack_bf16(o[n * 4 + 4] * i0, o[n * 4 + 5] * i0), pack_bf16(o[n * 4 + 6] * i1, o[n * 4 + 7] * i1));
            }
        };
        auto epilogue_publish = [&]() {
            asm volatile("fence.proxy.async.shared::cta;" ::: "memory");
            __syncwarp();
            if (lane == 0) mbar_arrive(bar(B_OF + cw));
        };
        auto softmax_first = [&](uint32_t (&pn)[32]) {
            float mx0, mx1;
            block_max(s, mx0, mx1);
            mref0 = mx0 * c; mref1 = mx1 * c;
            scale_shift(s, c, mref0, mref1);
            exp_pack(s, pn, l0, l1);
        };

        mbar_wait(bar(B_QF + 0), 0);
        mbar_wait(bar(B_KF + 0), 0);
        bar_sync(1 + cw, 256);
        wgmma_fence();
        issue_qk(0, 0);
        wgmma_commit();
        bar_arrive(2 - cw, 256);
        wgmma_wait<0>();
        fence_regs(s);
        release(B_KE + 0);
        softmax_first(pa);
        uint32_t okK = 0, okV = 0;
        float lf0 = 1.f, lf1 = 1.f;
        uint32_t vs = 0, vph = 0;

        auto step = [&](auto JC, int it, bool more, uint32_t (&pc)[32], uint32_t (&pn)[32]) {
            constexpr int J = decltype(JC)::value;
            const int t = it * NBLK + J;
            constexpr uint32_t ksc = J & 1, ksn = (J + 1) & 1;
            uint32_t vsn = vs + 1, vphn = vph;
            if (vsn == 3) { vsn = 0; vphn ^= 1; }
            const uint32_t qsn = (J == 3) ? ((it + 1) & 1) : (it & 1);
            if (J != 3 || more) {
                if (J == 3) mbar_wait(bar(B_QF + qsn), ((it + 1) >> 1) & 1);
                if (!okK) mbar_wait(bar(B_KF + ksn), ((t + 1) >> 1) & 1);
            }
            if (!okV) mbar_wait(bar(B_VF + vs), vph);
            bar_sync(1 + cw, 256);
            wgmma_fence();
            issue_qk(qsn, ksn);
            wgmma_commit();
            if (J == 0) {
                if (it > 0) epilogue(it - 1, lf0, lf1);
                wgmma_fence();
            }
            issue_pv(pc, vs, J != 0);
            wgmma_commit();
            bar_arrive(2 - cw, 256);
            if (J == 0) { if (it > 0) epilogue_publish(); }
            okK = mbar_test(bar(B_KF + ksc), ((t + 2) >> 1) & 1);
            okV = mbar_test(bar(B_VF + vsn), vphn);
            wgmma_wait<1>();
            fence_regs(s);
            if (J != 3 || more) release(B_KE + ksn);
            if (J == 3) {
                lf0 = l0; lf1 = l1;
                if (!(fabsf(mref0) <= 64.f)) mref0 = 0.f;
                if (!(fabsf(mref1) <= 64.f)) mref1 = 0.f;
                scale_shift(s, c, mref0, mref1);
                bool first_pass = true;
                while (true) {
                    exp_pack(s, pn, l0, l1);
                    float q0 = l0 + __shfl_xor_sync(0xffffffffu, l0, 1);
                    float q1 = l1 + __shfl_xor_sync(0xffffffffu, l1, 1);
                    q0 += __shfl_xor_sync(0xffffffffu, q0, 2);
                    q1 += __shfl_xor_sync(0xffffffffu, q1, 2);
                    const bool unsafe = !(q0 <= 1048576.f) || !(q1 <= 1048576.f) ||
                                        !(q0 >= 9.5367431640625e-7f) || !(q1 >= 9.5367431640625e-7f);
                    if (!first_pass || !__any_sync(0xffffffffu, unsafe)) break;
                    first_pass = false;
                    float d0, d1;
                    block_max(s, d0, d1);
                    mref0 += d0; mref1 += d1;
#pragma unroll
                    for (int n = 0; n < 16; n++) {
                        s[n * 4 + 0] -= d0; s[n * 4 + 1] -= d0;
                        s[n * 4 + 2] -= d1; s[n * 4 + 3] -= d1;
                    }
                }
                wgmma_wait<0>();
                fence_regs(o);
                fence_regs(pc);
                release(B_VE + vs);
            } else {
                float rs0, rs1;
                scale_shift(s, c, mref0, mref1);
                bool first_pass = true;
                while (true) {
                    exp_pack(s, pn, rs0, rs1);
                    const bool unsafe = !(rs0 <= 1048576.f) || !(rs1 <= 1048576.f);
                    if (!first_pass || !__any_sync(0xffffffffu, unsafe)) break;
                    first_pass = false;
                    wgmma_wait<0>();
                    fence_regs(o);
                    float d0, d1;
                    block_max(s, d0, d1);
                    d0 = fmaxf(d0, 0.f); d1 = fmaxf(d1, 0.f);
                    const float a0 = ex2(-d0), a1 = ex2(-d1);
                    mref0 += d0; mref1 += d1;
                    l0 *= a0; l1 *= a1;
#pragma unroll
                    for (int n = 0; n < 16; n++) {
                        o[n * 4 + 0] *= a0; o[n * 4 + 1] *= a0;
                        o[n * 4 + 2] *= a1; o[n * 4 + 3] *= a1;
                        s[n * 4 + 0] -= d0; s[n * 4 + 1] -= d0;
                        s[n * 4 + 2] -= d1; s[n * 4 + 3] -= d1;
                    }
                }
                wgmma_wait<0>();
                fence_regs(o);
                fence_regs(pc);
                release(B_VE + vs);
                l0 += rs0; l1 += rs1;
            }
            vs = vsn; vph = vphn;
        };

        for (int it = 0; it < ntiles; it++) {
            if (it == nstatic - 1) fetch_tail();
            const bool more = (it + 1 < ntiles);
            step(std::integral_constant<int, 0>{}, it, more, pa, pb);
            step(std::integral_constant<int, 1>{}, it, more, pb, pa);
            step(std::integral_constant<int, 2>{}, it, more, pa, pb);
            step(std::integral_constant<int, 3>{}, it, more, pb, pa);
        }
        epilogue(ntiles - 1, lf0, lf1);
        epilogue_publish();
        asm volatile("barrier.cluster.arrive.release.aligned;" ::: "memory");
        asm volatile("barrier.cluster.wait.acquire.aligned;" ::: "memory");
    }
}

typedef CUresult (*PFN_encodeTiled)(CUtensorMap*, CUtensorMapDataType, cuuint32_t, void*, const cuuint64_t*,
                                    const cuuint64_t*, const cuuint32_t*, const cuuint32_t*, CUtensorMapInterleave,
                                    CUtensorMapSwizzle, CUtensorMapL2promotion, CUtensorMapFloatOOBfill);

}

extern "C" void kernel_launch(void* const* d_in, const int* in_sizes, int n_in, void* d_out, int out_size) {
    static PFN_encodeTiled encode = nullptr;
    static int nclusters = 0;
    if (!encode) {
        void* fn = nullptr;
        cudaDriverEntryPointQueryResult qres;
        cudaGetDriverEntryPoint("cuTensorMapEncodeTiled", &fn, cudaEnableDefault, &qres);
        encode = (PFN_encodeTiled)fn;
        cudaFuncSetAttribute(gqa_fwd_kernel, cudaFuncAttributeMaxDynamicSharedMemorySize, SMEM_BYTES);
        cudaLaunchConfig_t cfg = {};
        cfg.gridDim = dim3(132, 1, 1);
        cfg.blockDim = dim3(384, 1, 1);
        cfg.dynamicSmemBytes = SMEM_BYTES;
        cudaLaunchAttribute attr[1];
        attr[0].id = cudaLaunchAttributeClusterDimension;
        attr[0].val.clusterDim.x = 2; attr[0].val.clusterDim.y = 1; attr[0].val.clusterDim.z = 1;
        cfg.attrs = attr; cfg.numAttrs = 1;
        int nc = 0;
        if (cudaOccupancyMaxActiveClusters(&nc, gqa_fwd_kernel, &cfg) != cudaSuccess || nc <= 0) nc = 64;
        nclusters = nc;
    }
    CUtensorMap tmQ, tmK, tmV, tmO;
    {
        cuuint64_t dims[3] = {HD, GROWS, GROUPS};
        cuuint64_t strides[2] = {HD * 2, (cuuint64_t)GROWS * HD * 2};
        cuuint32_t estr[3] = {1, 1, 1};
        cuuint32_t boxq[3] = {64, 128, 1};
        encode(&tmQ, CU_TENSOR_MAP_DATA_TYPE_BFLOAT16, 3, d_in[0], dims, strides, boxq, estr,
               CU_TENSOR_MAP_INTERLEAVE_NONE, CU_TENSOR_MAP_SWIZZLE_128B, CU_TENSOR_MAP_L2_PROMOTION_L2_128B,
               CU_TENSOR_MAP_FLOAT_OOB_FILL_NONE);
        cuuint32_t boxo[3] = {64, 64, 1};
        encode(&tmO, CU_TENSOR_MAP_DATA_TYPE_BFLOAT16, 3, d_out, dims, strides, boxo, estr,
               CU_TENSOR_MAP_INTERLEAVE_NONE, CU_TENSOR_MAP_SWIZZLE_128B, CU_TENSOR_MAP_L2_PROMOTION_L2_128B,
               CU_TENSOR_MAP_FLOAT_OOB_FILL_NONE);
    }
    {
        cuuint64_t dims[2] = {HD, (cuuint64_t)GROUPS * SK};
        cuuint64_t strides[1] = {HD * 2};
        cuuint32_t estr[2] = {1, 1};
        cuuint32_t box[2] = {64, 64};
        encode(&tmK, CU_TENSOR_MAP_DATA_TYPE_BFLOAT16, 2, d_in[1], dims, strides, box, estr,
               CU_TENSOR_MAP_INTERLEAVE_NONE, CU_TENSOR_MAP_SWIZZLE_128B, CU_TENSOR_MAP_L2_PROMOTION_L2_128B,
               CU_TENSOR_MAP_FLOAT_OOB_FILL_NONE);
        encode(&tmV, CU_TENSOR_MAP_DATA_TYPE_BFLOAT16, 2, d_in[2], dims, strides, box, estr,
               CU_TENSOR_MAP_INTERLEAVE_NONE, CU_TENSOR_MAP_SWIZZLE_128B, CU_TENSOR_MAP_L2_PROMOTION_L2_128B,
               CU_TENSOR_MAP_FLOAT_OOB_FILL_NONE);
    }
    cudaLaunchConfig_t cfg = {};
    cfg.gridDim = dim3(2 * nclusters, 1, 1);
    cfg.blockDim = dim3(384, 1, 1);
    cfg.dynamicSmemBytes = SMEM_BYTES;
    cfg.stream = cudaStreamPerThread;
    cudaLaunchAttribute attr[1];
    attr[0].id = cudaLaunchAttributeClusterDimension;
    attr[0].val.clusterDim.x = 2; attr[0].val.clusterDim.y = 1; attr[0].val.clusterDim.z = 1;
    cfg.attrs = attr; cfg.numAttrs = 1;
    cudaLaunchKernelEx(&cfg, gqa_fwd_kernel, tmQ, tmK, tmV, tmO, nclusters);
}
```
